```python
import torch

def _softmax(x, axis=-1):
    return torch.softmax(x, dim=axis)
def _gelu(x):
    return torch.nn.functional.gelu(x, approximate="tanh")
def _silu(x):
    return torch.nn.functional.silu(x)
def _sigmoid(x):
    return torch.sigmoid(x)
def _layernorm(x, axis=-1, eps=1e-5):
    m = x.mean(dim=axis, keepdim=True)
    v = x.var(dim=axis, keepdim=True, unbiased=False)
    return (x - m) / torch.sqrt(v + eps)
def _scatter_add(tgt, idx, src, axis=0):
    return tgt.clone().index_add_(axis, idx, src)
def _segment_sum(src, seg, n):
    out = torch.zeros((n,) + src.shape[1:], dtype=src.dtype)
    return out.index_add_(0, seg, src)
def _pad(x, pw):
    flat = tuple(v for pair in reversed(pw) for v in pair)
    return torch.nn.functional.pad(x, flat)

kernel_name = 'standalone__implicit_deq__vision'

def setup_inputs():

    _w = (lambda a: (lambda t: t.to(torch.bfloat16) if t.is_floating_point() else t)(torch.as_tensor(a)))
    H = W = 224
    C = 96
    Wz = (lambda *s: torch.randn(*s, dtype=torch.bfloat16) * 0.4)(C, C) * (0.3 / C ** 0.5)
    Wx = (lambda *s: torch.randn(*s, dtype=torch.bfloat16) * 0.4)(C, C) * (1.0 / C ** 0.5)
    bb = (lambda *s: torch.randn(*s, dtype=torch.bfloat16) * 0.4)(C) * 0.1
    return {
        "x": _w((lambda *s: torch.randn(*s, dtype=torch.bfloat16) * 0.4)(1, H, W, C)),
        "w_z": _w(Wz),
        "w_x": _w(Wx),
        "b": _w(bb),
    }

def reference(x, w_z, w_x, b):
    B, H, W, C = x.shape
    inj = torch.einsum("bhwc,cd->bhwd", x, w_x) + b
    z = torch.zeros_like(x)
    for _ in range(25):
        z = torch.tanh(torch.einsum("bhwc,cd->bhwd", z, w_z) + inj)
    return z
```

```cpp
#include <cuda.h>
#include <cuda_runtime.h>
#include <cuda_bf16.h>
#include <cuda_fp16.h>
#include <stdint.h>

#define NL 8
#define NWG 6
#define K1 11
#define ND 2
#define NTHREADS (NWG * 128)
#define NITER 25
#define NFIRST 2
#define LC 16
#define FENCE 1
#define ORD 0
#define DMODE 0
#define PTS 0x003333
#define SEG 0

#define SM_BASE 1024
#define SM_X SM_BASE
#define SM_INJ SM_X
#define SM_WZ (SM_X + 73728)
#define SM_PZ (SM_WZ + 18432)
#define SM_WRAW SM_PZ
#define SM_WX (SM_PZ + 320 * 192)
#define SM_WB (SM_WX + 18432)
#define SM_ONE (SM_WB + 1536)
#define SM_ZERO (SM_ONE + 128)
#define SM_BAR (SM_ZERO + 256)
#define BAR_X SM_BAR
#define BAR_WXL (SM_BAR + 48)
#define BAR_WZL (SM_BAR + 56)
#define BAR_WX (SM_BAR + 64)
#define BAR_WZ (SM_BAR + 72)
#define BAR_T (SM_BAR + 80)
#define SM_CNT (SM_BAR + 128)
#define SM_ST (SM_BAR + 160)
#define SM_PID (SM_BAR + 256)
#define SM_LUT (SM_PID + 768)
#define LUT_LO 0x2C00u
#define LUT_HI 0x4300u
#define LUT_N ((LUT_HI - LUT_LO) / 8 + 2)
#define SM_END (SM_LUT + LUT_N * LC * 4)
#define SM_TR SM_END

#define R8(c, d, o) c(d[o]), c(d[o + 1]), c(d[o + 2]), c(d[o + 3]), c(d[o + 4]), c(d[o + 5]), c(d[o + 6]), c(d[o + 7])
#define R24(c, d) R8(c, d, 0), R8(c, d, 8), R8(c, d, 16)
#define L24 "{%0,%1,%2,%3,%4,%5,%6,%7,%8,%9,%10,%11,%12,%13,%14,%15,%16,%17,%18,%19,%20,%21,%22,%23}"
#define L48 "{%0,%1,%2,%3,%4,%5,%6,%7,%8,%9,%10,%11,%12,%13,%14,%15,%16,%17,%18,%19,%20,%21,%22,%23,%24,%25,%26,%27,%28,%29,%30,%31,%32,%33,%34,%35,%36,%37,%38,%39,%40,%41,%42,%43,%44,%45,%46,%47}"
#define DESC_B(addr) (((uint64_t)(128 >> 4) << 16) | ((uint64_t)(256 >> 4) << 32) | (uint64_t)((addr) >> 4))
#define DESC_B6(addr) "l"(DESC_B(addr)), "l"(DESC_B(addr + 3072)), "l"(DESC_B(addr + 6144)), "l"(DESC_B(addr + 9216)), "l"(DESC_B(addr + 12288)), "l"(DESC_B(addr + 15360))

struct Desc6 { uint64_t d[6]; uint32_t dp; };
__device__ __forceinline__ void gemm_issue(uint32_t (&h)[24], const uint32_t (&a)[24], const Desc6& w) {
  asm volatile(
      "{\n.reg .pred t, f;\nsetp.eq.u32 t, 0, 0;\nsetp.ne.u32 f, 0, 0;\n"
      "wgmma.fence.sync.aligned;\n"
      "wgmma.mma_async.sync.aligned.m64n96k16.f16.f16.f16 " L24 ", {%24,%25,%26,%27}, %48, f, 1, 1, 1;\n"
      "wgmma.mma_async.sync.aligned.m64n96k16.f16.f16.f16 " L24 ", {%28,%29,%30,%31}, %49, t, 1, 1, 1;\n"
      "wgmma.mma_async.sync.aligned.m64n96k16.f16.f16.f16 " L24 ", {%32,%33,%34,%35}, %50, t, 1, 1, 1;\n"
      "wgmma.mma_async.sync.aligned.m64n96k16.f16.f16.f16 " L24 ", {%36,%37,%38,%39}, %51, t, 1, 1, 1;\n"
      "wgmma.mma_async.sync.aligned.m64n96k16.f16.f16.f16 " L24 ", {%40,%41,%42,%43}, %52, t, 1, 1, 1;\n"
      "wgmma.mma_async.sync.aligned.m64n96k16.f16.f16.f16 " L24 ", {%44,%45,%46,%47}, %53, t, 1, 1, 1;\n"
      "wgmma.commit_group.sync.aligned;\n}\n"
      : R24("=&r", h)
      : R24("r", a), "l"(w.d[0]), "l"(w.d[1]), "l"(w.d[2]), "l"(w.d[3]), "l"(w.d[4]), "l"(w.d[5])
      : "memory");
}
__device__ __forceinline__ void gemm_wait(uint32_t (&h)[24]) {
  asm volatile("wgmma.wait_group.sync.aligned 0;" : R24("+r", h)::"memory");
}
__device__ __forceinline__ void gemm_x(float (&d)[48], uint64_t desca) {
  asm volatile(
      "{\n.reg .pred t, f;\n.reg .b64 a;\nsetp.eq.u32 t, 0, 0;\nsetp.ne.u32 f, 0, 0;\n"
      "wgmma.fence.sync.aligned;\n"
      "wgmma.mma_async.sync.aligned.m64n96k16.f32.bf16.bf16 " L48 ", %49, %50, f, 1, 1, 0, 1;\n"
      "wgmma.mma_async.sync.aligned.m64n96k16.f32.bf16.bf16 " L48 ", %48, %51, t, 1, 1, 0, 1;\n"
      "add.s64 a, %48, 2;\n"
      "wgmma.mma_async.sync.aligned.m64n96k16.f32.bf16.bf16 " L48 ", a, %52, t, 1, 1, 0, 1;\n"
      "add.s64 a, %48, 256;\n"
      "wgmma.mma_async.sync.aligned.m64n96k16.f32.bf16.bf16 " L48 ", a, %53, t, 1, 1, 0, 1;\n"
      "add.s64 a, %48, 258;\n"
      "wgmma.mma_async.sync.aligned.m64n96k16.f32.bf16.bf16 " L48 ", a, %54, t, 1, 1, 0, 1;\n"
      "add.s64 a, %48, 512;\n"
      "wgmma.mma_async.sync.aligned.m64n96k16.f32.bf16.bf16 " L48 ", a, %55, t, 1, 1, 0, 1;\n"
      "add.s64 a, %48, 514;\n"
      "wgmma.mma_async.sync.aligned.m64n96k16.f32.bf16.bf16 " L48 ", a, %56, t, 1, 1, 0, 1;\n"
      "wgmma.commit_group.sync.aligned;\n"
      "wgmma.wait_group.sync.aligned 0;\n}\n"
      : R8("=&f", d, 0), R8("=&f", d, 8), R8("=&f", d, 16), R8("=&f", d, 24), R8("=&f", d, 32), R8("=&f", d, 40)
      : "l"(desca), "l"((uint64_t)(SM_ONE >> 4)), "l"(((uint64_t)(128 >> 4) << 32) | (uint64_t)(SM_WB >> 4)), DESC_B6(SM_WX)
      : "memory");
}

__device__ __forceinline__ uint32_t hadd2(uint32_t a, uint32_t b) { uint32_t r; asm("add.rn.f16x2 %0, %1, %2;" : "=r"(r) : "r"(a), "r"(b)); return r; }
__device__ __forceinline__ uint32_t tanh_mufu(uint32_t a) { uint32_t r;
 asm("tanh.approx.f16x2 %0, %1;" : "=r"(r) : "r"(a)); return r; }
__device__ __forceinline__ uint32_t pack_f16(float lo, float hi) { uint32_t r; asm("cvt.rn.f16x2.f32 %0, %1, %2;" : "=r"(r) : "f"(hi), "f"(lo)); return r; }
__device__ __forceinline__ uint32_t pack_bf16(float lo, float hi) { uint32_t r; asm("cvt.rn.bf16x2.f32 %0, %1, %2;" : "=r"(r) : "f"(hi), "f"(lo)); return r; }
__device__ __forceinline__ uint32_t bf16x2_to_f16x2(uint32_t w) { return pack_f16(__uint_as_float(w << 16), __uint_as_float(w & 0xffff0000u)); }
__device__ __forceinline__ uint32_t f16x2_to_bf16x2(uint32_t v) {
  float2 f = __half22float2(*reinterpret_cast<__half2*>(&v));
  return pack_bf16(f.x, f.y);
}
__device__ __forceinline__ uint32_t tanh_lut(uint32_t p, uint32_t base, uint32_t dp) {
  uint32_t xc, ia, a0, a1, d0, d1;
  asm("min.NaN.xorsign.abs.f16x2 %0, %1, %2;" : "=r"(xc) : "r"(p), "r"(LUT_HI * 0x10001u));
  xc &= 0xfff8fff8u;
  asm("{.reg .b32 t; abs.f16x2 t, %1; max.f16x2 %0, t, %2;}" : "=r"(ia) : "r"(xc), "r"((LUT_LO - 8) * 0x10001u));
  asm("dp2a.lo.u32.u32 %0, %1, %2, %3;" : "=r"(a0) : "r"(ia), "r"(dp), "r"(base));
  asm("dp2a.hi.u32.u32 %0, %1, %2, %3;" : "=r"(a1) : "r"(ia), "r"(dp), "r"(base));
  asm volatile("ld.shared.s16 %0, [%1+%2];" : "=r"(d0) : "r"(a0), "n"(SM_LUT - (int)(LUT_LO - 8) * (LC / 2) + 2));
  asm volatile("ld.shared.u32 %0, [%1+%2];" : "=r"(d1) : "r"(a1), "n"(SM_LUT - (int)(LUT_LO - 8) * (LC / 2)));
  return xc - d0 - d1;
}
__device__ __forceinline__ void sched_fence() { asm volatile("pmevent 0;"); }
template <class F>
__device__ __forceinline__ void act(const uint32_t (&h)[24], const uint32_t (&inj)[24], uint32_t lut, uint32_t dp, F&& put) {
#pragma unroll
  for (int q = 0; q < 12; q++) {
    const uint32_t p0 = hadd2(h[2 * q], inj[2 * q]), p1 = hadd2(h[2 * q + 1], inj[2 * q + 1]);
    const int rank = q * 5 % 12;
    if (2 * rank + 1 < NL) {
      put(2 * q, tanh_lut(p0, lut, dp));
      put(2 * q + 1, tanh_lut(p1, lut, dp));
    } else if (2 * rank < NL) {
      const uint32_t lo = tanh_lut(__byte_perm(p0, p1, 0x5410), lut, dp);
      uint32_t v0, v1;
      asm("{\n.reg .b16 a, b, c, d, l, m;\nmov.b32 {a, b}, %2;\nmov.b32 {c, d}, %3;\ntanh.approx.f16 b, b;\ntanh.approx.f16 d, d;\n"
          "mov.b32 {l, m}, %4;\nmov.b32 %0, {l, b};\nmov.b32 %1, {m, d};\n}" : "=r"(v0), "=r"(v1) : "r"(p0), "r"(p1), "r"(lo));
      put(2 * q, v0);
      put(2 * q + 1, v1);
    } else {
      put(2 * q, tanh_mufu(p0));
      put(2 * q + 1, tanh_mufu(p1));
    }
    if (SEG && q % (SEG ? SEG : 1) == SEG - 1 && q < 11) sched_fence();
  }
}

#define TR(i)
#define TRG(i)
#define TRV(i, v)
#define TRINIT()
#define TRDUMP()
#define SM_ALLOC (SM_END - SM_BASE + 1280)
#define TRI(n)
#define ITS_OFF 0

__device__ __forceinline__ void bar_sync(int id, int n) { asm volatile("bar.sync %0, %1;" ::"r"(id), "r"(n) : "memory"); }
__device__ __forceinline__ void mbar_init(uint32_t bar, int n) { asm volatile("mbarrier.init.shared::cta.b64 [%0], %1;" ::"r"(bar), "r"(n) : "memory"); }
__device__ __forceinline__ void mbar_expect(uint32_t bar, int bytes) { asm volatile("mbarrier.arrive.expect_tx.shared::cta.b64 _, [%0], %1;" ::"r"(bar), "r"(bytes) : "memory"); }
__device__ __forceinline__ void mbar_arrive(uint32_t bar) { asm volatile("mbarrier.arrive.shared::cta.b64 _, [%0];" ::"r"(bar) : "memory"); }
__device__ __forceinline__ void mbar_wait(uint32_t bar) {
  asm volatile("{\n.reg .pred p;\nW: mbarrier.try_wait.parity.shared::cta.b64 p, [%0], 0;\n@!p bra W;\n}" ::"r"(bar) : "memory");
}
__device__ __forceinline__ bool mbar_test(uint32_t bar) {
  uint32_t ok;
  asm volatile("{\n.reg .pred p;\nmbarrier.test_wait.parity.shared::cta.b64 p, [%1], 0;\nselp.u32 %0, 1, 0, p;\n}" : "=r"(ok) : "r"(bar) : "memory");
  return ok;
}
__device__ __forceinline__ void bulk_load(uint32_t dst, const void* src, int bytes, uint32_t bar) {
  asm volatile("cp.async.bulk.shared::cluster.global.mbarrier::complete_tx::bytes [%0], [%1], %2, [%3];" ::"r"(dst), "l"(src), "r"(bytes), "r"(bar) : "memory");
}
__device__ __forceinline__ void load_x(const CUtensorMap* tm, int tile, int row) {
  mbar_expect(BAR_X + tile * 8, 12288);
#pragma unroll
  for (int v = 0; v < 3; v++)
    asm volatile("cp.async.bulk.tensor.2d.shared::cluster.global.mbarrier::complete_tx::bytes [%0], [%1, {%3, %4}], [%2];"
                 ::"r"(SM_X + tile * 12288 + v * 4096), "l"(tm), "r"(BAR_X + tile * 8), "r"(v * 32), "r"(row + tile * 64) : "memory");
}
template <int P>
__device__ __forceinline__ void issue_x(const CUtensorMap* tm, int row) {
  int lo = NWG, hi = 0;
#pragma unroll
  for (int i = 0; i < NWG; i++)
    if (((PTS >> (4 * (NWG - 1 - i))) & 15) == P) { lo = min(lo, i); hi = i + 1; }
#pragma unroll 1
  for (int i = lo; i < hi; i++) load_x(tm, i, row);
}
__device__ __forceinline__ uint32_t lds32(uint32_t a) { uint32_t v; asm volatile("ld.shared.u32 %0, [%1];" : "=r"(v) : "r"(a) : "memory"); return v; }
__device__ __forceinline__ uint32_t lds16(uint32_t a) { uint32_t v; asm volatile("ld.shared.u16 %0, [%1];" : "=r"(v) : "r"(a) : "memory"); return v; }
__device__ __forceinline__ void sts32(uint32_t a, uint32_t v) { asm volatile("st.shared.u32 [%0], %1;" ::"r"(a), "r"(v) : "memory"); }
__device__ __forceinline__ void lds128(uint32_t& a, uint32_t& b, uint32_t& c, uint32_t& d, uint32_t addr) {
  asm volatile("ld.shared.v4.u32 {%0, %1, %2, %3}, [%4];" : "=r"(a), "=r"(b), "=r"(c), "=r"(d) : "r"(addr) : "memory");
}
__device__ __forceinline__ void sts128(uint32_t addr, uint32_t a, uint32_t b, uint32_t c, uint32_t d) {
  asm volatile("st.shared.v4.u32 [%0], {%1, %2, %3, %4};" ::"r"(addr), "r"(a), "r"(b), "r"(c), "r"(d) : "memory");
}
__device__ __forceinline__ void lds_row(uint32_t (&z)[24], int hf, uint32_t addr, bool p) {
  asm volatile("{\n.reg .pred p;\nsetp.ne.u32 p, %13, 0;\n@p ld.shared.v4.u32 {%0, %1, %2, %3}, [%12];\n"
               "@p ld.shared.v4.u32 {%4, %5, %6, %7}, [%12+64];\n@p ld.shared.v4.u32 {%8, %9, %10, %11}, [%12+128];\n}"
               : "+r"(z[hf]), "+r"(z[2 + hf]), "+r"(z[4 + hf]), "+r"(z[6 + hf]), "+r"(z[8 + hf]), "+r"(z[10 + hf]), "+r"(z[12 + hf]),
                 "+r"(z[14 + hf]), "+r"(z[16 + hf]), "+r"(z[18 + hf]), "+r"(z[20 + hf]), "+r"(z[22 + hf])
               : "r"(addr), "r"((uint32_t)p) : "memory");
}
__device__ __forceinline__ void sts_row(const uint32_t (&z)[24], int hf, uint32_t addr, bool p) {
  asm volatile("{\n.reg .pred p;\nsetp.ne.u32 p, %13, 0;\n@p st.shared.v4.u32 [%12], {%0, %1, %2, %3};\n"
               "@p st.shared.v4.u32 [%12+64], {%4, %5, %6, %7};\n@p st.shared.v4.u32 [%12+128], {%8, %9, %10, %11};\n}"
               ::"r"(z[hf]), "r"(z[2 + hf]), "r"(z[4 + hf]), "r"(z[6 + hf]), "r"(z[8 + hf]), "r"(z[10 + hf]), "r"(z[12 + hf]),
                 "r"(z[14 + hf]), "r"(z[16 + hf]), "r"(z[18 + hf]), "r"(z[20 + hf]), "r"(z[22 + hf]), "r"(addr), "r"((uint32_t)p) : "memory");
}
__device__ __forceinline__ void stg_row(const uint32_t (&z)[24], int hf, uint8_t* po, bool p) {
#pragma unroll
  for (int v = 0; v < 3; v++)
    asm volatile("{\n.reg .pred p;\nsetp.ne.u32 p, %5, 0;\n@p st.global.v4.u32 [%4], {%0, %1, %2, %3};\n}"
                 ::"r"(f16x2_to_bf16x2(z[8 * v + hf])), "r"(f16x2_to_bf16x2(z[8 * v + 2 + hf])), "r"(f16x2_to_bf16x2(z[8 * v + 4 + hf])),
                   "r"(f16x2_to_bf16x2(z[8 * v + 6 + hf])), "l"(po + v * 64), "r"((uint32_t)p));
}
__device__ __forceinline__ uint32_t fresh_tid() { uint32_t v; asm volatile("mov.u32 %0, %%tid.x;" : "=r"(v)); return v; }
__device__ __forceinline__ uint32_t nib_count(uint32_t m) { return (m * 0x11111111u) >> 28; }

__global__ void __launch_bounds__(NTHREADS, 1)
deq_kernel(const __grid_constant__ CUtensorMap tmx, const uint8_t* __restrict__ x, const uint8_t* __restrict__ wz, const uint8_t* __restrict__ wx,
           const uint8_t* __restrict__ bias, uint8_t* __restrict__ out, int rows_q, int rows_rem
           ) {
  const int tid = threadIdx.x;
  const int r0 = blockIdx.x * rows_q + min((int)blockIdx.x, rows_rem), nrows = rows_q + ((int)blockIdx.x < rows_rem);
#define DO_PFX(n) if (tid < n) asm volatile("prefetch.global.L2 [%0];" ::"l"(x + (size_t)r0 * 192 + tid * 128) : "memory")
  if (tid == NTHREADS - 1) {
    asm volatile("prefetch.tensormap [%0];" ::"l"(&tmx) : "memory");
    mbar_init(BAR_WXL, 1);
    asm volatile("fence.mbarrier_init.release.cluster;" ::: "memory");
    mbar_expect(BAR_WXL, 18432 + 192);
    bulk_load(SM_WRAW, wx, 18432, BAR_WXL);
    bulk_load(SM_WRAW + 36864, bias, 192, BAR_WXL);
#pragma unroll
    for (int i = 0; i < 16; i++)
      if (i != 6) mbar_init(SM_BAR + i * 8, i < 8 ? 1 : i < 10 ? 12 : 64);
    asm volatile("fence.mbarrier_init.release.cluster;" ::: "memory");
    mbar_expect(BAR_WZL, 18432);
    bulk_load(SM_WRAW + 18432, wz, 18432, BAR_WZL);
    issue_x<0>(&tmx, r0);
    sts32(SM_CNT, 0);
  }
  extern __shared__ __align__(1024) uint8_t smem[];
  if ((uint32_t)__cvta_generic_to_shared(smem) != SM_BASE) __trap();
  const int lane = tid & 31, g = lane >> 2, t = lane & 3;
  const int warp = __shfl_sync(0xffffffffu, tid >> 5, 0), wg = warp >> 2;
  TRINIT(); TR(0); TRG(15);
  if (NL > 0 && tid < (int)LUT_N) {
    uint32_t mid = LUT_LO - 8 + tid * 8 + 4;
    float xm = __half2float(__ushort_as_half((unsigned short)mid));
    uint32_t y = (tid == (int)LUT_N - 1) ? 0x3C00u : __half_as_ushort(__float2half_rn(tanhf(xm)));
    uint32_t d = ((tid == 0 ? 0u : mid - y) - 4u) << 16;
#pragma unroll
    for (int c = 0; c < LC / 4; c++) sts128(SM_LUT + tid * LC * 4 + ((c + lane * LC / 32) & (LC / 4 - 1)) * 16, d, d, d, d);
  }
  if (tid < 116) sts128(SM_WB + tid * 16, tid >= 96 && tid < 104 ? 0x3f00u : 0, 0, 0, 0);
  TR(1);
  __syncthreads();
  if (tid == NTHREADS - 32) issue_x<1>(&tmx, r0);
  {
    const bool isz = warp >= 12;
    const int kb = isz ? warp - 12 : warp;
    const int k = isz ? 32 * (kb >> 2) + 8 * (g >> 1) + 2 * (kb & 3) + (g & 1) : 8 * kb + g;
    const uint32_t src = SM_WRAW + (isz ? 18432 : 0) + k * 192 + t * 16;
    const uint32_t dst = (isz ? SM_WZ : SM_WX) + (kb >> 1) * 3072 + (kb & 1) * 128 + lane * 4;
    uint32_t w[12];
    mbar_wait(isz ? BAR_WZL : BAR_WXL);
    TR(2);
    if (tid == NTHREADS - 32) issue_x<2>(&tmx, r0);
#pragma unroll
    for (int v = 0; v < 3; v++) lds128(w[4 * v], w[4 * v + 1], w[4 * v + 2], w[4 * v + 3], src + v * 64);
    if (tid < 48) sts32(SM_WB + (tid >> 4) * 512 + (tid & 3) * 128 + ((tid >> 2) & 3) * 4, lds32(SM_WRAW + 36864 + tid * 4));
#pragma unroll
    for (int j = 0; j < 12; j++) sts32(dst + j * 256, isz ? bf16x2_to_f16x2(w[j]) : w[j]);
    asm volatile("fence.proxy.async.shared::cta;" ::: "memory");
    __syncwarp();
    if (lane == 0) mbar_arrive(isz ? BAR_WZ : BAR_WX);
  }
  mbar_wait(BAR_WX);
  TR(7);
  if (tid == NTHREADS - 32) {
    issue_x<3>(&tmx, r0);
    if ((PTS & 15) >= 4) { mbar_wait(BAR_X); issue_x<4>(&tmx, r0); }
    if ((PTS & 15) >= 5) { mbar_wait(BAR_X + 8); issue_x<5>(&tmx, r0); }
    if ((PTS & 15) >= 6) { mbar_wait(BAR_X + 16); issue_x<6>(&tmx, r0); }
  }
  sts32(SM_ST + warp * 4, nrows);
  if (wg) mbar_wait(BAR_WZ);
  mbar_wait(BAR_X + wg * 8);
  TR(3);

  uint32_t inj[24], h[24];
  {
    float d[48];
    gemm_x(d, ((uint64_t)1 << 16) | ((uint64_t)(512 >> 4) << 32) | ((uint64_t)2 << 62) | ((SM_X + wg * 12288) >> 4));
    TRI(31);
    if (!wg) mbar_wait(BAR_WZ);
    bar_sync(1 + wg, 128);
#pragma unroll
    for (int r = 0; r < 24; r++) inj[r] = pack_f16(d[2 * r], d[2 * r + 1]);
    const int s0 = warp * 16 + g;
#pragma unroll
    for (int r = 0; r < 24; r++) h[r] = 0;
    sched_fence();
    sts_row(inj, 0, SM_INJ + s0 * 192 + t * 16, true);
    sts_row(inj, 1, SM_INJ + s0 * 192 + t * 16 + 8 * 192, true);
  }
  TR(4);
  uint32_t lut = (tid & (LC - 1)) * 4;
  Desc6 wd;
#pragma unroll
  for (int k = 0; k < 6; k++) wd.d[k] = DESC_B(SM_WZ + k * 3072);
  wd.dp = LC / 2 * 0x01000001u;
  int n = K1 - 1 + ITS_OFF;
#pragma unroll 1
  for (;;) {
    uint32_t z[24];
#pragma unroll 1
    do {
      act(h, inj, lut, wd.dp, [&](int r, uint32_t v) { z[r] = v; });
      gemm_issue(h, z, wd);
      gemm_wait(h);
      TRI(n);
    } while ((--n & (ITS_OFF - 1)) != 0);
    uint32_t df[2] = {0, 0}, id[2] = {0, 0}, total = 0;
    if (rows_q >= 0) {
      act(h, inj, lut, wd.dp, [&](int r, uint32_t v) { df[r & 1] |= v ^ z[r]; inj[r] = v; });
      const uint32_t t1 = fresh_tid(), pid = SM_PID + (t1 >> 5) * 32 + ((t1 >> 1) & 14);
      id[0] = lds16(pid);
      id[1] = lds16(pid + 16);
      total = lds32(SM_ST + (t1 >> 5) * 4);
    }
    const bool last = (int)total < 0;
    if (last) TR(5); else TR(8);
    const uint32_t tf = fresh_tid(), tq16 = (tf & 3) * 16, ln = tf & 31, g4 = tf & 28, s0 = (tf >> 5) * 16 + (g4 >> 2);
    total &= 0xffff;
    bool alive[2];
    uint32_t am[2];
#pragma unroll
    for (int hf = 0; hf < 2; hf++) {
      if (!last)
        id[hf] = s0 + hf * 8;
      const uint32_t ch = __ballot_sync(0xffffffffu, df[hf] != 0);
      alive[hf] = s0 + hf * 8 < total && !last && ((ch >> g4) & 15);
      am[hf] = __ballot_sync(0xffffffffu, alive[hf]) & 0x11111111u;
    }
    if (!last) {
      const uint32_t n0 = nib_count(am[0]), nal = n0 + nib_count(am[1]), lt = (1u << g4) - 1;
      uint32_t cnt = 0;
      asm volatile("{\n.reg .pred p;\nsetp.eq.u32 p, %3, 0;\n@p atom.shared.add.u32 %0, [%1], %2;\n}"
                   : "+r"(cnt) : "r"(SM_CNT + ln), "r"(0x10000 + nal), "r"(ln) : "memory");
      cnt = __reduce_or_sync(0xffffffffu, cnt);
      const int b = cnt & 0xffff;
#pragma unroll
      for (int hf = 0; hf < 2; hf++) {
        const uint32_t slot = b + (hf ? n0 : 0) + nib_count(am[hf] & lt);
        sts_row(inj, hf, SM_PZ + slot * 192 + tq16, alive[hf]);
        if (alive[hf]) asm volatile("st.shared.u16 [%0], %1;" ::"r"(SM_PID + slot * 2), "h"((uint16_t)id[hf]) : "memory");
      }
      __syncwarp();
      const int e = (cnt >> 16) == NWG * 4 - 1 ? NWG * 64 : b + (int)nal;
      const int c = min(e, (int)ln * 64 + 64) - max(b, (int)ln * 64);
      if (c > 0) asm volatile("mbarrier.arrive.shared::cta.b64 _, [%0], %1;" ::"r"(BAR_T + ln * 8), "r"(c) : "memory");
      TR(9);
    }
#pragma unroll
    for (int hf = 0; hf < 2; hf++) stg_row(inj, hf, out + (size_t)(r0 + id[hf]) * 192 + tq16, s0 + hf * 8 < total && !alive[hf]);
    if (last) break;
    TR(11);
    mbar_wait(BAR_T + (tf >> 7) * 8);
    total = lds32(SM_CNT) & 0xffff;
    if (tf >= 384 && (tf >> 7) * 64 >= total) break;
#pragma unroll
    for (int hf = 0; hf < 2; hf++) {
      id[hf] = lds16(SM_PID + (s0 + hf * 8) * 2);
#pragma unroll
      for (int v = 0; v < 3; v++)
        lds128(inj[8 * v + hf], inj[8 * v + 2 + hf], inj[8 * v + 4 + hf], inj[8 * v + 6 + hf], SM_PZ + (s0 + hf * 8) * 192 + tq16 + v * 64);
    }
    TRV(12, total);
    if ((tf >> 7) * 64 >= total) break;
    sts32(SM_ST + (tf >> 5) * 4, total | 0x80000000u);
    const uint32_t m0 = s0 < total ? 0xffffffffu : 0, m1 = s0 + 8 < total ? 0xffffffffu : 0;
#pragma unroll
    for (int r = 0; r < 24; r++) z[r] = inj[r] & (r & 1 ? m1 : m0);
    const uint32_t a0 = (m0 ? SM_INJ + id[0] * 192 : SM_ZERO) + tq16, a1 = (m1 ? SM_INJ + id[1] * 192 : SM_ZERO) + tq16;
    lut = (tf & (LC - 1)) * 4;
    TR(10);
    gemm_issue(h, z, wd);
#pragma unroll
    for (int v = 0; v < 3; v++) {
      lds128(inj[8 * v], inj[8 * v + 2], inj[8 * v + 4], inj[8 * v + 6], a0 + v * 64);
      lds128(inj[8 * v + 1], inj[8 * v + 3], inj[8 * v + 5], inj[8 * v + 7], a1 + v * 64);
    }
    gemm_wait(h);
    asm volatile("{\n.reg .pred p;\n.reg .b32 t;\nlop3.b32 t, %0, %1, %2, 0x80;\nlop3.b32 t, t, %3, %4, 0x80;\nsetp.eq.u32 p, t, %5;\n@p pmevent 0;\n}"
                 ::"r"(inj[0]), "r"(inj[8]), "r"(inj[16]), "r"(inj[1]), "r"(inj[9]), "r"(inj[17]));
    TRI(15);
    n = NITER - K1 - 1;
  }
  TR(6); TRG(14); TRDUMP();
}

typedef CUresult (*EncodeFn)(CUtensorMap*, CUtensorMapDataType, cuuint32_t, void*, const cuuint64_t*, const cuuint64_t*,
                             const cuuint32_t*, const cuuint32_t*, CUtensorMapInterleave, CUtensorMapSwizzle,
                             CUtensorMapL2promotion, CUtensorMapFloatOOBfill);
#define PROMO CU_TENSOR_MAP_L2_PROMOTION_L2_128B

extern "C" void kernel_launch(void* const* d_in, const int* in_sizes, int n_in, void* d_out, int out_size) {
  static int sms = 0;
  static EncodeFn encode = nullptr;
  const int M = in_sizes[0] / 96;
  if (!sms) {
    int dev = 0;
    cudaGetDevice(&dev);
    cudaDeviceGetAttribute(&sms, cudaDevAttrMultiProcessorCount, dev);
    cudaFuncSetAttribute(deq_kernel, cudaFuncAttributeMaxDynamicSharedMemorySize, SM_ALLOC);
    cudaDriverEntryPointQueryResult qr;
    cudaGetDriverEntryPoint("cuTensorMapEncodeTiled", (void**)&encode, cudaEnableDefault, &qr);
  }
  const int need = (M + NWG * 64 - 1) / (NWG * 64), grid = sms > need ? sms : need;
  CUtensorMap tmx;
  cuuint64_t dims[2] = {96, (cuuint64_t)M}, strides[1] = {192};
  cuuint32_t box[2] = {32, 64}, estr[2] = {1, 1};
  encode(&tmx, CU_TENSOR_MAP_DATA_TYPE_BFLOAT16, 2, d_in[0], dims, strides, box, estr, CU_TENSOR_MAP_INTERLEAVE_NONE,
         CU_TENSOR_MAP_SWIZZLE_64B, PROMO, CU_TENSOR_MAP_FLOAT_OOB_FILL_NONE);
  deq_kernel<<<grid, NTHREADS, SM_ALLOC>>>(tmx, (const uint8_t*)d_in[0], (const uint8_t*)d_in[1], (const uint8_t*)d_in[2],
                                           (const uint8_t*)d_in[3], (uint8_t*)d_out, M / grid, M % grid
    );
}
```

```cpp
#include <cuda.h>
#include <cuda_runtime.h>
#include <cuda_bf16.h>
#include <cuda_fp16.h>
#include <stdint.h>

#define NITER 25
#define K1 11
#define NWG 6
#define NTHREADS (NWG * 128)
#define LUTQ 0x10d
#define QORD 0x1963742b5a08ull
#define QORD2 0x510369482b7aull
#define QORD3 0x7465130298abull
static_assert(K1 >= 3 && K1 <= 16 && NITER - K1 >= 2 && NITER - K1 <= 16, "iteration counter layout");

#define SM_BASE 1024
#define SM_X SM_BASE
#define SM_INJ SM_X
#define SM_WZ (SM_X + 73728)
#define SM_PZ (SM_WZ + 18432)
#define SM_WRAW SM_PZ
#define SM_WX (SM_PZ + 288 * 192)
#define SM_WB (SM_WX + 18432)
#define SM_ONE (SM_WB + 1536)
#define SM_ZERO (SM_ONE + 128)
#define SM_BAR (SM_ZERO + 256)
#define BAR_X SM_BAR
#define BAR_WXL (SM_BAR + 48)
#define BAR_WZL (SM_BAR + 56)
#define BAR_WX (SM_BAR + 64)
#define BAR_WZ (SM_BAR + 72)
#define BAR_T (SM_BAR + 80)
#define BAR_XD (SM_BAR + 128)
#define SM_CNT (SM_BAR + 136)
#define SM_FLAG (SM_BAR + 144)
#define SM_PID (SM_BAR + 256)
#define SM_SID (SM_PID + 768)
#define SM_LUT (SM_SID + 768)
#define LUT_LO 0x2740u
#define LUT_HI 0x4480u
#define LUT_N ((LUT_HI - LUT_LO) / 8 + 1)
#define SM_END (SM_LUT + LUT_N * 64)

#define R8(c, d, o) c(d[o]), c(d[o + 1]), c(d[o + 2]), c(d[o + 3]), c(d[o + 4]), c(d[o + 5]), c(d[o + 6]), c(d[o + 7])
#define R24(c, d) R8(c, d, 0), R8(c, d, 8), R8(c, d, 16)
#define ROW(c, z, hf) c(z[hf]), c(z[2 + hf]), c(z[4 + hf]), c(z[6 + hf]), c(z[8 + hf]), c(z[10 + hf]), c(z[12 + hf]), \
                      c(z[14 + hf]), c(z[16 + hf]), c(z[18 + hf]), c(z[20 + hf]), c(z[22 + hf])
#define L24 "{%0,%1,%2,%3,%4,%5,%6,%7,%8,%9,%10,%11,%12,%13,%14,%15,%16,%17,%18,%19,%20,%21,%22,%23}"
#define L48 "{%0,%1,%2,%3,%4,%5,%6,%7,%8,%9,%10,%11,%12,%13,%14,%15,%16,%17,%18,%19,%20,%21,%22,%23,%24,%25,%26,%27,%28,%29,%30,%31,%32,%33,%34,%35,%36,%37,%38,%39,%40,%41,%42,%43,%44,%45,%46,%47}"
#define DESC_B(addr) (((uint64_t)(128 >> 4) << 16) | ((uint64_t)(256 >> 4) << 32) | (uint64_t)((addr) >> 4))

struct Consts { uint64_t wz[6]; uint32_t dp; };

__device__ __forceinline__ void gemm_z_issue(uint32_t (&h)[24], const uint32_t (&a)[24], const Consts& c) {
  asm volatile(
      "{\n.reg .pred t, f;\nsetp.eq.u32 t, 0, 0;\nsetp.ne.u32 f, 0, 0;\n"
      "wgmma.fence.sync.aligned;\n"
      "wgmma.mma_async.sync.aligned.m64n96k16.f16.f16.f16 " L24 ", {%24,%25,%26,%27}, %48, f, 1, 1, 1;\n"
      "wgmma.mma_async.sync.aligned.m64n96k16.f16.f16.f16 " L24 ", {%28,%29,%30,%31}, %49, t, 1, 1, 1;\n"
      "wgmma.mma_async.sync.aligned.m64n96k16.f16.f16.f16 " L24 ", {%32,%33,%34,%35}, %50, t, 1, 1, 1;\n"
      "wgmma.mma_async.sync.aligned.m64n96k16.f16.f16.f16 " L24 ", {%36,%37,%38,%39}, %51, t, 1, 1, 1;\n"
      "wgmma.mma_async.sync.aligned.m64n96k16.f16.f16.f16 " L24 ", {%40,%41,%42,%43}, %52, t, 1, 1, 1;\n"
      "wgmma.mma_async.sync.aligned.m64n96k16.f16.f16.f16 " L24 ", {%44,%45,%46,%47}, %53, t, 1, 1, 1;\n"
      "wgmma.commit_group.sync.aligned;\n}\n"
      : R24("=&r", h)
      : R24("r", a), "l"(c.wz[0]), "l"(c.wz[1]), "l"(c.wz[2]), "l"(c.wz[3]), "l"(c.wz[4]), "l"(c.wz[5])
      : "memory");
}
__device__ __forceinline__ void gemm_wait(uint32_t (&h)[24]) { asm volatile("wgmma.wait_group.sync.aligned 0;" : R24("+r", h)::"memory"); }
__device__ __forceinline__ void gemm_z(uint32_t (&h)[24], const uint32_t (&a)[24], const Consts& c) { gemm_z_issue(h, a, c); gemm_wait(h); }
__device__ __forceinline__ void gemm_x(float (&d)[48], uint64_t desca) {
  asm volatile(
      "{\n.reg .pred t, f;\n.reg .b64 a;\nsetp.eq.u32 t, 0, 0;\nsetp.ne.u32 f, 0, 0;\n"
      "wgmma.fence.sync.aligned;\n"
      "wgmma.mma_async.sync.aligned.m64n96k16.f32.bf16.bf16 " L48 ", %49, %50, f, 1, 1, 0, 1;\n"
      "wgmma.mma_async.sync.aligned.m64n96k16.f32.bf16.bf16 " L48 ", %48, %51, t, 1, 1, 0, 1;\n"
      "add.s64 a, %48, 2;\n"
      "wgmma.mma_async.sync.aligned.m64n96k16.f32.bf16.bf16 " L48 ", a, %52, t, 1, 1, 0, 1;\n"
      "add.s64 a, %48, 256;\n"
      "wgmma.mma_async.sync.aligned.m64n96k16.f32.bf16.bf16 " L48 ", a, %53, t, 1, 1, 0, 1;\n"
      "add.s64 a, %48, 258;\n"
      "wgmma.mma_async.sync.aligned.m64n96k16.f32.bf16.bf16 " L48 ", a, %54, t, 1, 1, 0, 1;\n"
      "add.s64 a, %48, 512;\n"
      "wgmma.mma_async.sync.aligned.m64n96k16.f32.bf16.bf16 " L48 ", a, %55, t, 1, 1, 0, 1;\n"
      "add.s64 a, %48, 514;\n"
      "wgmma.mma_async.sync.aligned.m64n96k16.f32.bf16.bf16 " L48 ", a, %56, t, 1, 1, 0, 1;\n"
      "wgmma.commit_group.sync.aligned;\n"
      "wgmma.wait_group.sync.aligned 0;\n}\n"
      : R8("=&f", d, 0), R8("=&f", d, 8), R8("=&f", d, 16), R8("=&f", d, 24), R8("=&f", d, 32), R8("=&f", d, 40)
      : "l"(desca), "l"((uint64_t)(SM_ONE >> 4)), "l"(((uint64_t)(128 >> 4) << 32) | (uint64_t)(SM_WB >> 4)), "l"(DESC_B(SM_WX)),
        "l"(DESC_B(SM_WX + 3072)), "l"(DESC_B(SM_WX + 6144)), "l"(DESC_B(SM_WX + 9216)), "l"(DESC_B(SM_WX + 12288)), "l"(DESC_B(SM_WX + 15360))
      : "memory");
}

__device__ __forceinline__ uint32_t hadd2(uint32_t a, uint32_t b) { uint32_t r; asm("add.rn.f16x2 %0, %1, %2;" : "=r"(r) : "r"(a), "r"(b)); return r; }
__device__ __forceinline__ uint32_t pack_f16(float lo, float hi) { uint32_t r; asm("cvt.rn.f16x2.f32 %0, %1, %2;" : "=r"(r) : "f"(hi), "f"(lo)); return r; }
__device__ __forceinline__ uint32_t bf16x2_to_f16x2(uint32_t w) { return pack_f16(__uint_as_float(w << 16), __uint_as_float(w & 0xffff0000u)); }
__device__ __forceinline__ uint32_t f16x2_to_bf16x2(uint32_t v) {
  uint32_t r;
  asm volatile("{\n.reg .b16 a, b;\n.reg .f32 c, d;\nmov.b32 {a, b}, %1;\ncvt.f32.f16 c, a;\ncvt.f32.f16 d, b;\ncvt.rn.bf16x2.f32 %0, d, c;\n}" : "=r"(r) : "r"(v));
  return r;
}
__device__ __forceinline__ uint32_t tanh_mufu(uint32_t a) { uint32_t r; asm("tanh.approx.f16x2 %0, %1;" : "=r"(r) : "r"(a)); return r; }
__device__ __forceinline__ uint32_t tanh_lut(uint32_t p, uint32_t lut, uint32_t dp) {
  uint32_t xc, ia, a0, a1, d0, d1;
  asm("min.NaN.xorsign.abs.f16x2 %0, %1, %2;" : "=r"(xc) : "r"(p), "r"(LUT_HI * 0x10001u));
  xc &= 0xfff8fff8u;
  asm("{.reg .b32 t; abs.f16x2 t, %1; max.f16x2 %0, t, %2;}" : "=r"(ia) : "r"(xc), "r"(LUT_LO * 0x10001u));
  asm("dp2a.lo.u32.u32 %0, %1, %2, %3;" : "=r"(a0) : "r"(ia), "r"(dp), "r"(lut));
  asm("dp2a.hi.u32.u32 %0, %1, %2, %3;" : "=r"(a1) : "r"(ia), "r"(dp), "r"(lut));
  asm("ld.shared.s16 %0, [%1+%2];" : "=r"(d0) : "r"(a0), "n"(SM_LUT - LUT_LO * 8 + 2));
  asm("ld.shared.u32 %0, [%1+%2];" : "=r"(d1) : "r"(a1), "n"(SM_LUT - LUT_LO * 8));
  return xc - d0 - d1;
}
template <uint64_t ORD, int I0 = 0, int I1 = 12, class F>
__device__ __forceinline__ void act(const uint32_t (&h)[24], const uint32_t (&inj)[24], uint32_t lut, uint32_t dp, F&& put) {
#pragma unroll
  for (int i = I0; i < I1; i++) {
    const int q = (int)((ORD >> (4 * i)) & 15);
    const uint32_t p0 = hadd2(h[2 * q], inj[2 * q]), p1 = hadd2(h[2 * q + 1], inj[2 * q + 1]);
    put(2 * q, (LUTQ >> q) & 1 ? tanh_lut(p0, lut, dp) : tanh_mufu(p0));
    put(2 * q + 1, (LUTQ >> q) & 1 ? tanh_lut(p1, lut, dp) : tanh_mufu(p1));
  }
}

__device__ __forceinline__ void sched_fence() { asm volatile("pmevent 0;" ::: "memory"); }
__device__ __forceinline__ uint32_t fresh_tid() { uint32_t v; asm volatile("mov.u32 %0, %%tid.x;" : "=r"(v)); return v; }
__device__ __forceinline__ bool elect_one() {
  uint32_t p;
  asm volatile("{\n.reg .pred p;\nelect.sync _|p, 0xffffffff;\nselp.u32 %0, 1, 0, p;\n}" : "=r"(p));
  return p;
}
__device__ __forceinline__ void bar_sync(int id) { asm volatile("bar.sync %0, 128;" ::"r"(id) : "memory"); }
__device__ __forceinline__ void mbar_init(uint32_t bar, int n) { asm volatile("mbarrier.init.shared::cta.b64 [%0], %1;" ::"r"(bar), "r"(n) : "memory"); }
__device__ __forceinline__ void mbar_expect(uint32_t bar, int bytes) { asm volatile("mbarrier.arrive.expect_tx.shared::cta.b64 _, [%0], %1;" ::"r"(bar), "r"(bytes) : "memory"); }
__device__ __forceinline__ void mbar_arrive(uint32_t bar, int n) { asm volatile("mbarrier.arrive.shared::cta.b64 _, [%0], %1;" ::"r"(bar), "r"(n) : "memory"); }
__device__ __forceinline__ void mbar_wait(uint32_t bar) {
  asm volatile("{\n.reg .pred p;\nW: mbarrier.try_wait.parity.shared::cta.b64 p, [%0], 0;\n@!p bra W;\n}" ::"r"(bar) : "memory");
}
__device__ __forceinline__ void bulk_load(uint32_t dst, const void* src, int bytes, uint32_t bar) {
  asm volatile("cp.async.bulk.shared::cluster.global.mbarrier::complete_tx::bytes [%0], [%1], %2, [%3];" ::"r"(dst), "l"(src), "r"(bytes), "r"(bar) : "memory");
}
__device__ __forceinline__ void load_x(const CUtensorMap* tm, int tile, int row) {
  mbar_expect(BAR_X + tile * 8, 12288);
  asm volatile("cp.async.bulk.tensor.3d.shared::cluster.global.mbarrier::complete_tx::bytes [%0], [%1, {%3, %4, %3}], [%2];"
               ::"r"(SM_X + tile * 12288), "l"(tm), "r"(BAR_X + tile * 8), "r"(0), "r"(row + tile * 64) : "memory");
}
__device__ __forceinline__ uint32_t lds16(uint32_t a) { uint32_t v; asm volatile("ld.shared.u16 %0, [%1];" : "=r"(v) : "r"(a) : "memory"); return v; }
__device__ __forceinline__ uint32_t lds32(uint32_t a) { uint32_t v; asm volatile("ld.shared.u32 %0, [%1];" : "=r"(v) : "r"(a) : "memory"); return v; }
__device__ __forceinline__ void sts32(uint32_t a, uint32_t v) { asm volatile("st.shared.u32 [%0], %1;" ::"r"(a), "r"(v) : "memory"); }
__device__ __forceinline__ void sts128(uint32_t addr, uint32_t a, uint32_t b) {
  asm volatile("st.shared.v4.u32 [%0], {%1, %2, %2, %2};" ::"r"(addr), "r"(a), "r"(b) : "memory");
}
__device__ __forceinline__ void lds_row(uint32_t (&z)[24], int hf, uint32_t addr) {
  asm volatile("ld.shared.v4.u32 {%0, %1, %2, %3}, [%12];\nld.shared.v4.u32 {%4, %5, %6, %7}, [%12+64];\nld.shared.v4.u32 {%8, %9, %10, %11}, [%12+128];"
               : ROW("=&r", z, hf) : "r"(addr) : "memory");
}
__device__ __forceinline__ void sts_row(const uint32_t (&z)[24], int hf, uint32_t addr, bool p) {
  asm volatile("{\n.reg .pred p;\nsetp.ne.u32 p, %13, 0;\n@p st.shared.v4.u32 [%12], {%0, %1, %2, %3};\n"
               "@p st.shared.v4.u32 [%12+64], {%4, %5, %6, %7};\n@p st.shared.v4.u32 [%12+128], {%8, %9, %10, %11};\n}"
               ::ROW("r", z, hf), "r"(addr), "r"((uint32_t)p) : "memory");
}
__device__ __forceinline__ void stg_quad(const uint32_t (&z)[24], int r, uint8_t* po, bool p) {
  asm volatile("{\n.reg .pred p;\nsetp.ne.u32 p, %5, 0;\n@p st.global.v4.u32 [%4], {%0, %1, %2, %3};\n}"
               ::"r"(f16x2_to_bf16x2(z[r])), "r"(f16x2_to_bf16x2(z[r + 2])), "r"(f16x2_to_bf16x2(z[r + 4])), "r"(f16x2_to_bf16x2(z[r + 6])), "l"(po), "r"((uint32_t)p) : "memory");
}
__device__ __forceinline__ void stg_row(const uint32_t (&z)[24], int hf, uint8_t* po, bool p) {
  asm volatile("{\n.reg .pred p;\nsetp.ne.u32 p, %13, 0;\n@p st.global.v4.u32 [%12], {%0, %1, %2, %3};\n"
               "@p st.global.v4.u32 [%12+64], {%4, %5, %6, %7};\n@p st.global.v4.u32 [%12+128], {%8, %9, %10, %11};\n}"
               ::ROW("r", z, hf), "l"(po), "r"((uint32_t)p) : "memory");
}
__device__ __forceinline__ uint32_t nib_count(uint32_t m) { return (m * 0x11111111u) >> 28; }

__device__ __forceinline__ float rbf(float v) { return __bfloat162float(__float2bfloat16_rn(v)); }
__device__ __forceinline__ void plain_row(const uint8_t* x, const uint8_t* wz, const uint8_t* wx, const uint8_t* bias, uint8_t* out, int row, int ln) {
  typedef const __nv_bfloat16* P;
  float z[3], inj[3] = {0, 0, 0};
#pragma unroll
  for (int j = 0; j < 3; j++) z[j] = __bfloat162float(((P)x)[(size_t)row * 96 + j * 32 + ln]);
#pragma unroll 1
  for (int it = 0; it <= NITER; it++) {
    const P w = (P)(it ? wz : wx) + ln;
    float a[3] = {0, 0, 0};
#pragma unroll
    for (int j = 0; j < 3; j++)
#pragma unroll 4
      for (int k = 0; k < 32; k++) {
        const float zk = __shfl_sync(0xffffffffu, z[j], k);
#pragma unroll
        for (int c = 0; c < 3; c++) a[c] = fmaf(zk, __bfloat162float(w[(j * 32 + k) * 96 + c * 32]), a[c]);
      }
#pragma unroll
    for (int c = 0; c < 3; c++) {
      if (it) {
        z[c] = rbf(tanhf(rbf(rbf(a[c]) + inj[c])));
      } else {
        inj[c] = rbf(rbf(a[c]) + __bfloat162float(((P)bias)[c * 32 + ln]));
        z[c] = 0;
      }
    }
  }
#pragma unroll
  for (int c = 0; c < 3; c++) ((__nv_bfloat16*)out)[(size_t)row * 96 + c * 32 + ln] = __float2bfloat16_rn(z[c]);
}

__global__ void __launch_bounds__(NTHREADS, 1)
deq_kernel(const __grid_constant__ CUtensorMap tmx, const uint8_t* __restrict__ x, const uint8_t* __restrict__ wz, const uint8_t* __restrict__ wx,
           const uint8_t* __restrict__ bias, uint8_t* __restrict__ out, int rows_q, int rows_rem, const __grid_constant__ Consts cs) {
  const int tid = threadIdx.x, warp = __shfl_sync(0xffffffffu, tid >> 5, 0), wg = warp >> 2;
  const int r0 = blockIdx.x * rows_q + min((int)blockIdx.x, rows_rem), nrows = rows_q + ((int)blockIdx.x < rows_rem);
  if (warp == NWG * 4 - 1 && elect_one()) {
    asm volatile("prefetch.tensormap [%0];" ::"l"(&tmx) : "memory");
    mbar_init(BAR_WXL, 1);
    mbar_init(BAR_WZL, 1);
    mbar_init(BAR_X, 1);
    mbar_init(BAR_X + 8, 1);
    asm volatile("fence.mbarrier_init.release.cluster;" ::: "memory");
    mbar_expect(BAR_WXL, 18432 + 192);
    bulk_load(SM_WRAW, wx, 18432, BAR_WXL);
    bulk_load(SM_WRAW + 36864, bias, 192, BAR_WXL);
    mbar_expect(BAR_WZL, 18432);
    bulk_load(SM_WRAW + 18432, wz, 18432, BAR_WZL);
#pragma unroll 1
    for (int i = 0; i < 2; i++) load_x(&tmx, i, r0);
  }
  if (tid >= 706 && tid < 721 && (tid & ~1) != 710) {
    const int i = tid - 704;
    mbar_init(SM_BAR + i * 8, i < 8 ? 1 : i < 10 ? 12 : i < 16 ? 64 : NWG);
    asm volatile("fence.mbarrier_init.release.cluster;" ::: "memory");
  }
  if (tid >= 672 && tid < 676) sts32(SM_CNT + (tid - 672) * 4, 0);
  extern __shared__ __align__(1024) uint8_t smem[];
  if ((uint32_t)__cvta_generic_to_shared(smem) != SM_BASE) __trap();
  const int lane = tid & 31, g = lane >> 2, t = lane & 3;
#pragma unroll 1
  for (int e = tid; e < (int)LUT_N; e += NTHREADS) {
    const uint32_t lo = LUT_LO + e * 8;
    const uint32_t d = (lo - __half_as_ushort(__float2half_rn(tanhf(__half2float(__ushort_as_half(lo + 4)))))) << 16;
#pragma unroll
    for (int c = 0; c < 4; c++) sts128(SM_LUT + e * 64 + ((c + (lane >> 1)) & 3) * 16, d, d);
  }
  if (tid < 116) sts128(SM_WB + tid * 16, tid >= 96 && tid < 104 ? 0x3f00u : 0, 0);
  __syncthreads();
  {
    const bool isz = warp >= 12;
    const int kb = isz ? warp - 12 : warp;
    const int k = isz ? 32 * (kb >> 2) + 8 * (g >> 1) + 2 * (kb & 3) + (g & 1) : 8 * kb + g;
    const uint32_t dst = (isz ? SM_WZ : SM_WX) + (kb >> 1) * 3072 + (kb & 1) * 128 + lane * 4;
    uint32_t w[24], big = 0;
    mbar_wait(isz ? BAR_WZL : BAR_WXL);
    if (isz) mbar_wait(BAR_WX);
    if (warp == NWG * 4 - 1 && elect_one()) load_x(&tmx, 2, r0);
    lds_row(w, 0, SM_WRAW + (isz ? 18432 : 0) + k * 192 + t * 16);
    if (tid < 48) sts32(SM_WB + (tid >> 4) * 512 + (tid & 3) * 128 + ((tid >> 2) & 3) * 4, lds32(SM_WRAW + 36864 + tid * 4));
#pragma unroll
    for (int q = 0; q < 12; q++) {
      sts32(dst + q * 256, isz ? bf16x2_to_f16x2(w[2 * q]) : w[2 * q]);
      big |= w[2 * q];
    }
    if (isz && (big & 0x40004000u)) sts32(SM_FLAG + 4, 1);
    asm volatile("fence.proxy.async.shared::cta;" ::: "memory");
    __syncwarp();
    if (lane == 0) mbar_arrive(isz ? BAR_WZ : BAR_WX, 1);
  }
  mbar_wait(BAR_WX);
  if (warp == NWG * 4 - 1 && elect_one()) {
#pragma unroll 1
    for (int i = 3; i < NWG; i++) {
      if (i > 3) mbar_wait(BAR_X + (2 * i - 6) * 8);
      load_x(&tmx, i, r0);
    }
  }
  mbar_wait(BAR_X + wg * 8);

  uint32_t inj[24], h[24];
  {
    float d[48];
    gemm_x(d, ((uint64_t)1 << 16) | ((uint64_t)(512 >> 4) << 32) | ((uint64_t)2 << 62) | ((SM_X + wg * 12288) >> 4));
#pragma unroll
    for (int r = 0; r < 24; r++) inj[r] = pack_f16(d[2 * r], d[2 * r + 1]);
  }
  uint32_t lut = (tid & 15) * 4;
  {
    uint32_t z[24];
    sched_fence();
#pragma unroll
    for (int r = 0; r < 24; r++)
      z[r] = (LUTQ >> (r >> 1)) & 1 ? tanh_lut(inj[r], lut, cs.dp) : tanh_mufu(inj[r]);
    if (!((inj[0] | inj[2] | inj[4]) & 0x70007000u) || !((inj[1] | inj[3] | inj[5]) & 0x70007000u)) sts32(SM_FLAG, 1);
    const uint32_t t0 = fresh_tid();
    mbar_wait(BAR_WZ);
    bar_sync(1 + (t0 >> 7));
    if ((t0 & 127) == 0) mbar_arrive(BAR_XD, 1);
    const uint32_t a = SM_INJ + ((t0 >> 5) * 16 + ((t0 >> 2) & 7)) * 192 + (t0 & 3) * 16;
    gemm_z_issue(h, z, cs);
    sched_fence();
    sts_row(inj, 0, a, true);
    sts_row(inj, 1, a + 8 * 192, true);
    gemm_wait(h);
  }
  int n = 16 + K1 - 2;
#pragma unroll 1
  for (;;) {
    uint32_t z[24];
#pragma unroll 1
    do {
      act<QORD>(h, inj, lut, cs.dp, [&](int r, uint32_t v) { z[r] = v; });
      gemm_z(h, z, cs);
    } while ((--n & 15) != 0);
    if (n == 0) {
      const uint32_t t1 = fresh_tid(), ids = lds32(SM_SID + (t1 & ~3));
      uint8_t* const po = out + (size_t)r0 * 192 + (t1 & 3) * 16;
      uint8_t* const p0 = po + (ids & 0xffff) * 192;
      uint8_t* const p1 = po + (ids >> 16) * 192;
      auto put = [&](int r, uint32_t v) { z[r] = v; };
      auto flush = [&](int i) {
        const int v = (int)((QORD3 >> (4 * i + 2)) & 3);
        stg_quad(z, 8 * v, p0 + v * 64, !(ids & 0x8000u));
        stg_quad(z, 8 * v + 1, p1 + v * 64, !(ids & 0x80000000u));
      };
      act<QORD3, 0, 5>(h, inj, lut, cs.dp, put);
      flush(0);
      act<QORD3, 5, 9>(h, inj, lut, cs.dp, put);
      sched_fence();
      flush(4);
      act<QORD3, 9, 12>(h, inj, lut, cs.dp, put);
      flush(8);
      break;
    }
    uint32_t df[2] = {0, 0};
    if (rows_q >= 0)
      act<QORD2>(h, inj, lut, cs.dp, [&](int r, uint32_t v) { df[r & 1] |= v ^ z[r]; inj[r] = v; });
    const uint32_t tf = fresh_tid(), tq16 = (tf & 3) * 16, ln = tf & 31, g4 = tf & 28, s0 = (tf >> 5) * 16 + (g4 >> 2);
    bool alive[2];
    uint32_t am[2];
#pragma unroll
    for (int hf = 0; hf < 2; hf++) {
      uint32_t ch = __ballot_sync(0xffffffffu, df[hf] != 0 && s0 + hf * 8 < nrows);
      ch |= ch >> 2;
      am[hf] = (ch | ch >> 1) & 0x11111111u;
      alive[hf] = (am[hf] >> g4) & 1;
    }
    {
      const uint32_t n0 = nib_count(am[0]), nal = n0 + nib_count(am[1]), lt = (1u << g4) - 1;
      uint32_t cnt = 0;
      asm volatile("{\n.reg .pred p;\nsetp.eq.u32 p, %3, 0;\n@p atom.shared.add.u32 %0, [%1], %2;\n}"
                   : "+r"(cnt) : "r"(SM_CNT + ln), "r"(0x10000 + nal), "r"(ln) : "memory");
      cnt = __reduce_or_sync(0xffffffffu, cnt);
      const int b = cnt & 0xffff;
      if (b + nal > 288) mbar_wait(BAR_XD);
#pragma unroll
      for (int hf = 0; hf < 2; hf++) {
        const uint32_t slot = b + (hf ? n0 : 0) + nib_count(am[hf] & lt);
        sts_row(inj, hf, SM_PZ + slot * 192 + tq16, alive[hf]);
        if (alive[hf]) asm volatile("st.shared.u16 [%0], %1;" ::"r"(SM_PID + slot * 2), "h"((uint16_t)(s0 + hf * 8)) : "memory");
      }
      __syncwarp();
      const int e = (cnt >> 16) == NWG * 4 - 1 ? NWG * 64 : b + (int)nal;
      const int c = min(e, (int)ln * 64 + 64) - max(b, (int)ln * 64);
      if (c > 0) mbar_arrive(BAR_T + ln * 8, c);
    }
    sched_fence();
#pragma unroll
    for (int r = 0; r < 24; r++) z[r] = f16x2_to_bf16x2(inj[r]);
#pragma unroll
    for (int hf = 0; hf < 2; hf++) stg_row(z, hf, out + (size_t)(r0 + s0) * 192 + hf * 8 * 192 + tq16, s0 + hf * 8 < nrows && !alive[hf]);
    const uint32_t tk = tf >> 7, s1 = tk * 64 + ((tf & 127) >> 2);
    mbar_wait(BAR_T + tk * 8);
    const uint32_t total = lds32(SM_CNT) & 0xffff;
    if (tk * 64 >= total) break;
    const uint32_t id0 = lds16(SM_PID + s1 * 2), id1 = lds16(SM_PID + s1 * 2 + 64);
    const bool v0 = s1 < total, v1 = s1 + 32 < total;
    uint32_t zp[24];
    lds_row(zp, 0, SM_PZ + s1 * 192 + tq16);
    lds_row(zp, 1, SM_PZ + (s1 + 32) * 192 + tq16);
    lds_row(inj, 0, (v0 ? SM_INJ + id0 * 192 : SM_ZERO) + tq16);
    lds_row(inj, 1, (v1 ? SM_INJ + id1 * 192 : SM_ZERO) + tq16);
    sts32(SM_SID + (tf & ~3), (v0 ? id0 : 0x8000) | (v1 ? id1 : 0x8000) << 16);
    lut = (tf & 15) * 4;
    sched_fence();
#pragma unroll
    for (int r = 0; r < 24; r++) z[r] = (r & 1 ? v1 : v0) ? zp[r] : 0;
    gemm_z(h, z, cs);
    asm volatile("{\n.reg .pred p;\n.reg .b32 t;\nshf.l.wrap.b32 t, %0, %1, %6;\nshf.l.wrap.b32 t, %2, %3, t;\nshf.l.wrap.b32 t, %4, %5, t;\n"
                 "setp.eq.u32 p, t, 1;\n@p pmevent 0;\n}"
                 ::"r"(inj[0]), "r"(inj[8]), "r"(inj[16]), "r"(inj[1]), "r"(inj[9]), "r"(inj[17]), "r"(h[0]));
    n = NITER - K1 - 1;
  }
  mbar_wait(BAR_XD);
  const uint32_t some = lds32(SM_FLAG), all = lds32(SM_FLAG + 4);
  if (some | all) {
    __syncthreads();
    const uint32_t t1 = fresh_tid(), l1 = t1 & 31;
#pragma unroll 1
    for (int row = (t1 >> 5) * 16, end = min(row + 16, nrows); row < end; row++) {
      const uint32_t m = lds32(SM_INJ + row * 192 + l1 * 4) | lds32(SM_INJ + row * 192 + 64 + l1 * 4);
      if (all || !__any_sync(0xffffffffu, m & 0x70007000u)) plain_row(x, wz, wx, bias, out, r0 + row, l1);
    }
  }
}

typedef CUresult (*EncodeFn)(CUtensorMap*, CUtensorMapDataType, cuuint32_t, void*, const cuuint64_t*, const cuuint64_t*,
                             const cuuint32_t*, const cuuint32_t*, CUtensorMapInterleave, CUtensorMapSwizzle,
                             CUtensorMapL2promotion, CUtensorMapFloatOOBfill);

extern "C" void kernel_launch(void* const* d_in, const int* in_sizes, int n_in, void* d_out, int out_size) {
  static int sms = 0;
  static EncodeFn encode = nullptr;
  if (!sms) {
    int dev = 0;
    cudaGetDevice(&dev);
    cudaDeviceGetAttribute(&sms, cudaDevAttrMultiProcessorCount, dev);
    cudaFuncSetAttribute(deq_kernel, cudaFuncAttributeMaxDynamicSharedMemorySize, SM_END - SM_BASE);
    cudaDriverEntryPointQueryResult qr;
    cudaGetDriverEntryPoint("cuTensorMapEncodeTiled", (void**)&encode, cudaEnableDefault, &qr);
  }
  const int M = in_sizes[0] / 96, need = (M + NWG * 64 - 1) / (NWG * 64), grid = sms > need ? sms : need;
  CUtensorMap tmx;
  cuuint64_t dims[3] = {32, (cuuint64_t)M, 3}, strides[2] = {192, 64};
  cuuint32_t box[3] = {32, 64, 3}, estr[3] = {1, 1, 1};
  encode(&tmx, CU_TENSOR_MAP_DATA_TYPE_BFLOAT16, 3, d_in[0], dims, strides, box, estr, CU_TENSOR_MAP_INTERLEAVE_NONE,
         CU_TENSOR_MAP_SWIZZLE_64B, CU_TENSOR_MAP_L2_PROMOTION_L2_128B, CU_TENSOR_MAP_FLOAT_OOB_FILL_NONE);
  Consts cs;
  for (int k = 0; k < 6; k++) cs.wz[k] = DESC_B(SM_WZ + k * 3072);
  cs.dp = 0x08000008u;
  deq_kernel<<<grid, NTHREADS, SM_END - SM_BASE>>>(tmx, (const uint8_t*)d_in[0], (const uint8_t*)d_in[1], (const uint8_t*)d_in[2],
                                                   (const uint8_t*)d_in[3], (uint8_t*)d_out, M / grid, M % grid, cs);
}
```
